```python
import torch

def _softmax(x, axis=-1):
    return torch.softmax(x, dim=axis)
def _gelu(x):
    return torch.nn.functional.gelu(x, approximate="tanh")
def _silu(x):
    return torch.nn.functional.silu(x)
def _sigmoid(x):
    return torch.sigmoid(x)
def _layernorm(x, axis=-1, eps=1e-5):
    m = x.mean(dim=axis, keepdim=True)
    v = x.var(dim=axis, keepdim=True, unbiased=False)
    return (x - m) / torch.sqrt(v + eps)
def _scatter_add(tgt, idx, src, axis=0):
    return tgt.clone().index_add_(axis, idx, src)
def _segment_sum(src, seg, n):
    out = torch.zeros((n,) + src.shape[1:], dtype=src.dtype)
    return out.index_add_(0, seg, src)
def _pad(x, pw):
    flat = tuple(v for pair in reversed(pw) for v in pair)
    return torch.nn.functional.pad(x, flat)

kernel_name = 'gated_mix__sliding_block__glu_gated_glu__prompt'

def setup_inputs():

    _w = (lambda a: (lambda t: t.to(torch.bfloat16) if t.is_floating_point() else t)(torch.as_tensor(a)))
    def _A_setup():
        B, S, D = 1, 2048, 448
        return {
            "x": _w((lambda *s: torch.randn(*s, dtype=torch.bfloat16) * 0.05)(B, S, D)),
            "wqkv": _w((lambda *s: torch.randn(*s, dtype=torch.bfloat16) * 1.6)(D, 3 * D)),
            "wo": _w((lambda *s: torch.randn(*s, dtype=torch.bfloat16) * 0.05)(D, D)),
        }
    _A_in = _A_setup()

    def _B_setup():
        B, S, D, F = 1, 2048, 448, 1792
        return {
            "x": _w((lambda *s: torch.randn(*s, dtype=torch.bfloat16) * 0.05)(B, S, D)),
            "w_gate": _w((lambda *s: torch.randn(*s, dtype=torch.bfloat16) * 3.2)(D, F)),
            "w_up": _w((lambda *s: torch.randn(*s, dtype=torch.bfloat16) * 0.2)(D, F)),
            "w_down": _w((lambda *s: torch.randn(*s, dtype=torch.bfloat16) * 0.2)(F, D)),
        }
    _B_in = _B_setup()

    return {
        "A_x": _A_in["x"],
        "A_wqkv": _A_in["wqkv"],
        "A_wo": _A_in["wo"],
        "B_x": _B_in["x"],
        "B_w_gate": _B_in["w_gate"],
        "B_w_up": _B_in["w_up"],
        "B_w_down": _B_in["w_down"],
        "gate_w": _w((lambda *s: torch.randn(*s, dtype=torch.bfloat16) * 0.05)(448) * 16.0),
    }

def reference(A_x, A_wqkv, A_wo, B_x, B_w_gate, B_w_up, B_w_down, gate_w):
    def _A_ref(x, wqkv, wo):
        B, S, D = x.shape
        H = 16; Dh = D // H; W = 256
        qkv = (lambda x, *d: x.permute(*d))((x @ wqkv).reshape(B, S, 3, H, Dh), 2, 0, 3, 1, 4)
        q, k, v = qkv[0], qkv[1], qkv[2]
        scores = torch.einsum("bhqd,bhkd->bhqk", q, k) * (Dh ** -0.5)
        idx = torch.arange(S)
        mask = (idx[:, None] - idx[None, :] >= 0) & (idx[:, None] - idx[None, :] < W)
        scores = torch.where(mask[None, None], scores, -1e9)
        p = _softmax(scores, axis=-1)
        o = torch.einsum("bhqk,bhkd->bhqd", p, v)
        return (lambda x, *d: x.permute(*d))(o, 0, 2, 1, 3).reshape(B, S, D) @ wo

    def _B_ref(x, w_gate, w_up, w_down):
        g = torch.einsum("bsd,df->bsf", x, w_gate)
        u = torch.einsum("bsd,df->bsf", x, w_up)
        h = _sigmoid(g) * u
        return torch.einsum("bsf,fd->bsd", h, w_down)

    x = A_x
    g = _sigmoid((x * gate_w).sum(-1, keepdims=True))
    a = _A_ref(x, A_wqkv, A_wo)
    b = _B_ref(x, B_w_gate, B_w_up, B_w_down)
    return g * a + (1 - g) * b
```

```cpp
#include <cuda_runtime.h>
#include <cuda.h>
#include <cuda_bf16.h>
#include <stdint.h>

namespace {

template<int N> struct WG;
template<> struct WG<32> {
  template<int TB> static __device__ __forceinline__ void rs(float (&d)[16], uint32_t a0, uint32_t a1, uint32_t a2, uint32_t a3, uint64_t db, int sd) {
    asm volatile("{\n.reg .pred p;\nsetp.ne.b32 p, %21, 0;\nwgmma.mma_async.sync.aligned.m64n32k16.f32.bf16.bf16 {%0, %1, %2, %3, %4, %5, %6, %7, %8, %9, %10, %11, %12, %13, %14, %15}, {%16, %17, %18, %19}, %20, p, 1, 1, %22;\n}"
      : "+f"(d[0]), "+f"(d[1]), "+f"(d[2]), "+f"(d[3]), "+f"(d[4]), "+f"(d[5]), "+f"(d[6]), "+f"(d[7]), "+f"(d[8]), "+f"(d[9]), "+f"(d[10]), "+f"(d[11]), "+f"(d[12]), "+f"(d[13]), "+f"(d[14]), "+f"(d[15]) : "r"(a0), "r"(a1), "r"(a2), "r"(a3), "l"(db), "r"(sd), "n"(TB));
  }
  template<int TB> static __device__ __forceinline__ void rsz(float (&d)[16], uint32_t a0, uint32_t a1, uint32_t a2, uint32_t a3, uint64_t db) {
    asm volatile("wgmma.mma_async.sync.aligned.m64n32k16.f32.bf16.bf16 {%0, %1, %2, %3, %4, %5, %6, %7, %8, %9, %10, %11, %12, %13, %14, %15}, {%16, %17, %18, %19}, %20, 0, 1, 1, %21;"
      : "=f"(d[0]), "=f"(d[1]), "=f"(d[2]), "=f"(d[3]), "=f"(d[4]), "=f"(d[5]), "=f"(d[6]), "=f"(d[7]), "=f"(d[8]), "=f"(d[9]), "=f"(d[10]), "=f"(d[11]), "=f"(d[12]), "=f"(d[13]), "=f"(d[14]), "=f"(d[15]) : "r"(a0), "r"(a1), "r"(a2), "r"(a3), "l"(db), "n"(TB));
  }
};
template<> struct WG<64> {
  template<int TB> static __device__ __forceinline__ void ss(float (&d)[32], uint64_t da, uint64_t db, int sd) {
    asm volatile("{\n.reg .pred p;\nsetp.ne.b32 p, %34, 0;\nwgmma.mma_async.sync.aligned.m64n64k16.f32.bf16.bf16 {%0, %1, %2, %3, %4, %5, %6, %7, %8, %9, %10, %11, %12, %13, %14, %15, %16, %17, %18, %19, %20, %21, %22, %23, %24, %25, %26, %27, %28, %29, %30, %31}, %32, %33, p, 1, 1, 0, %35;\n}"
      : "+f"(d[0]), "+f"(d[1]), "+f"(d[2]), "+f"(d[3]), "+f"(d[4]), "+f"(d[5]), "+f"(d[6]), "+f"(d[7]), "+f"(d[8]), "+f"(d[9]), "+f"(d[10]), "+f"(d[11]), "+f"(d[12]), "+f"(d[13]), "+f"(d[14]), "+f"(d[15]), "+f"(d[16]), "+f"(d[17]), "+f"(d[18]), "+f"(d[19]), "+f"(d[20]), "+f"(d[21]), "+f"(d[22]), "+f"(d[23]), "+f"(d[24]), "+f"(d[25]), "+f"(d[26]), "+f"(d[27]), "+f"(d[28]), "+f"(d[29]), "+f"(d[30]), "+f"(d[31]) : "l"(da), "l"(db), "r"(sd), "n"(TB));
  }
  template<int TB> static __device__ __forceinline__ void rs(float (&d)[32], uint32_t a0, uint32_t a1, uint32_t a2, uint32_t a3, uint64_t db, int sd) {
    asm volatile("{\n.reg .pred p;\nsetp.ne.b32 p, %37, 0;\nwgmma.mma_async.sync.aligned.m64n64k16.f32.bf16.bf16 {%0, %1, %2, %3, %4, %5, %6, %7, %8, %9, %10, %11, %12, %13, %14, %15, %16, %17, %18, %19, %20, %21, %22, %23, %24, %25, %26, %27, %28, %29, %30, %31}, {%32, %33, %34, %35}, %36, p, 1, 1, %38;\n}"
      : "+f"(d[0]), "+f"(d[1]), "+f"(d[2]), "+f"(d[3]), "+f"(d[4]), "+f"(d[5]), "+f"(d[6]), "+f"(d[7]), "+f"(d[8]), "+f"(d[9]), "+f"(d[10]), "+f"(d[11]), "+f"(d[12]), "+f"(d[13]), "+f"(d[14]), "+f"(d[15]), "+f"(d[16]), "+f"(d[17]), "+f"(d[18]), "+f"(d[19]), "+f"(d[20]), "+f"(d[21]), "+f"(d[22]), "+f"(d[23]), "+f"(d[24]), "+f"(d[25]), "+f"(d[26]), "+f"(d[27]), "+f"(d[28]), "+f"(d[29]), "+f"(d[30]), "+f"(d[31]) : "r"(a0), "r"(a1), "r"(a2), "r"(a3), "l"(db), "r"(sd), "n"(TB));
  }
  template<int TB> static __device__ __forceinline__ void rsz(float (&d)[32], uint32_t a0, uint32_t a1, uint32_t a2, uint32_t a3, uint64_t db) {
    asm volatile("wgmma.mma_async.sync.aligned.m64n64k16.f32.bf16.bf16 {%0, %1, %2, %3, %4, %5, %6, %7, %8, %9, %10, %11, %12, %13, %14, %15, %16, %17, %18, %19, %20, %21, %22, %23, %24, %25, %26, %27, %28, %29, %30, %31}, {%32, %33, %34, %35}, %36, 0, 1, 1, %37;"
      : "=f"(d[0]), "=f"(d[1]), "=f"(d[2]), "=f"(d[3]), "=f"(d[4]), "=f"(d[5]), "=f"(d[6]), "=f"(d[7]), "=f"(d[8]), "=f"(d[9]), "=f"(d[10]), "=f"(d[11]), "=f"(d[12]), "=f"(d[13]), "=f"(d[14]), "=f"(d[15]), "=f"(d[16]), "=f"(d[17]), "=f"(d[18]), "=f"(d[19]), "=f"(d[20]), "=f"(d[21]), "=f"(d[22]), "=f"(d[23]), "=f"(d[24]), "=f"(d[25]), "=f"(d[26]), "=f"(d[27]), "=f"(d[28]), "=f"(d[29]), "=f"(d[30]), "=f"(d[31]) : "r"(a0), "r"(a1), "r"(a2), "r"(a3), "l"(db), "n"(TB));
  }
};
template<> struct WG<128> {
  template<int TB> static __device__ __forceinline__ void ss(float (&d)[64], uint64_t da, uint64_t db, int sd) {
    asm volatile("{\n.reg .pred p;\nsetp.ne.b32 p, %66, 0;\nwgmma.mma_async.sync.aligned.m64n128k16.f32.bf16.bf16 {%0, %1, %2, %3, %4, %5, %6, %7, %8, %9, %10, %11, %12, %13, %14, %15, %16, %17, %18, %19, %20, %21, %22, %23, %24, %25, %26, %27, %28, %29, %30, %31, %32, %33, %34, %35, %36, %37, %38, %39, %40, %41, %42, %43, %44, %45, %46, %47, %48, %49, %50, %51, %52, %53, %54, %55, %56, %57, %58, %59, %60, %61, %62, %63}, %64, %65, p, 1, 1, 0, %67;\n}"
      : "+f"(d[0]), "+f"(d[1]), "+f"(d[2]), "+f"(d[3]), "+f"(d[4]), "+f"(d[5]), "+f"(d[6]), "+f"(d[7]), "+f"(d[8]), "+f"(d[9]), "+f"(d[10]), "+f"(d[11]), "+f"(d[12]), "+f"(d[13]), "+f"(d[14]), "+f"(d[15]), "+f"(d[16]), "+f"(d[17]), "+f"(d[18]), "+f"(d[19]), "+f"(d[20]), "+f"(d[21]), "+f"(d[22]), "+f"(d[23]), "+f"(d[24]), "+f"(d[25]), "+f"(d[26]), "+f"(d[27]), "+f"(d[28]), "+f"(d[29]), "+f"(d[30]), "+f"(d[31]), "+f"(d[32]), "+f"(d[33]), "+f"(d[34]), "+f"(d[35]), "+f"(d[36]), "+f"(d[37]), "+f"(d[38]), "+f"(d[39]), "+f"(d[40]), "+f"(d[41]), "+f"(d[42]), "+f"(d[43]), "+f"(d[44]), "+f"(d[45]), "+f"(d[46]), "+f"(d[47]), "+f"(d[48]), "+f"(d[49]), "+f"(d[50]), "+f"(d[51]), "+f"(d[52]), "+f"(d[53]), "+f"(d[54]), "+f"(d[55]), "+f"(d[56]), "+f"(d[57]), "+f"(d[58]), "+f"(d[59]), "+f"(d[60]), "+f"(d[61]), "+f"(d[62]), "+f"(d[63]) : "l"(da), "l"(db), "r"(sd), "n"(TB));
  }
  template<int TB> static __device__ __forceinline__ void ssz(float (&d)[64], uint64_t da, uint64_t db) {
    asm volatile("wgmma.mma_async.sync.aligned.m64n128k16.f32.bf16.bf16 {%0, %1, %2, %3, %4, %5, %6, %7, %8, %9, %10, %11, %12, %13, %14, %15, %16, %17, %18, %19, %20, %21, %22, %23, %24, %25, %26, %27, %28, %29, %30, %31, %32, %33, %34, %35, %36, %37, %38, %39, %40, %41, %42, %43, %44, %45, %46, %47, %48, %49, %50, %51, %52, %53, %54, %55, %56, %57, %58, %59, %60, %61, %62, %63}, %64, %65, 0, 1, 1, 0, %66;"
      : "=f"(d[0]), "=f"(d[1]), "=f"(d[2]), "=f"(d[3]), "=f"(d[4]), "=f"(d[5]), "=f"(d[6]), "=f"(d[7]), "=f"(d[8]), "=f"(d[9]), "=f"(d[10]), "=f"(d[11]), "=f"(d[12]), "=f"(d[13]), "=f"(d[14]), "=f"(d[15]), "=f"(d[16]), "=f"(d[17]), "=f"(d[18]), "=f"(d[19]), "=f"(d[20]), "=f"(d[21]), "=f"(d[22]), "=f"(d[23]), "=f"(d[24]), "=f"(d[25]), "=f"(d[26]), "=f"(d[27]), "=f"(d[28]), "=f"(d[29]), "=f"(d[30]), "=f"(d[31]), "=f"(d[32]), "=f"(d[33]), "=f"(d[34]), "=f"(d[35]), "=f"(d[36]), "=f"(d[37]), "=f"(d[38]), "=f"(d[39]), "=f"(d[40]), "=f"(d[41]), "=f"(d[42]), "=f"(d[43]), "=f"(d[44]), "=f"(d[45]), "=f"(d[46]), "=f"(d[47]), "=f"(d[48]), "=f"(d[49]), "=f"(d[50]), "=f"(d[51]), "=f"(d[52]), "=f"(d[53]), "=f"(d[54]), "=f"(d[55]), "=f"(d[56]), "=f"(d[57]), "=f"(d[58]), "=f"(d[59]), "=f"(d[60]), "=f"(d[61]), "=f"(d[62]), "=f"(d[63]) : "l"(da), "l"(db), "n"(TB));
  }
};
template<> struct WG<184> {
  template<int TB> static __device__ __forceinline__ void ss(float (&d)[92], uint64_t da, uint64_t db, int sd) {
    asm volatile("{\n.reg .pred p;\nsetp.ne.b32 p, %94, 0;\nwgmma.mma_async.sync.aligned.m64n184k16.f32.bf16.bf16 {%0, %1, %2, %3, %4, %5, %6, %7, %8, %9, %10, %11, %12, %13, %14, %15, %16, %17, %18, %19, %20, %21, %22, %23, %24, %25, %26, %27, %28, %29, %30, %31, %32, %33, %34, %35, %36, %37, %38, %39, %40, %41, %42, %43, %44, %45, %46, %47, %48, %49, %50, %51, %52, %53, %54, %55, %56, %57, %58, %59, %60, %61, %62, %63, %64, %65, %66, %67, %68, %69, %70, %71, %72, %73, %74, %75, %76, %77, %78, %79, %80, %81, %82, %83, %84, %85, %86, %87, %88, %89, %90, %91}, %92, %93, p, 1, 1, 0, %95;\n}"
      : "+f"(d[0]), "+f"(d[1]), "+f"(d[2]), "+f"(d[3]), "+f"(d[4]), "+f"(d[5]), "+f"(d[6]), "+f"(d[7]), "+f"(d[8]), "+f"(d[9]), "+f"(d[10]), "+f"(d[11]), "+f"(d[12]), "+f"(d[13]), "+f"(d[14]), "+f"(d[15]), "+f"(d[16]), "+f"(d[17]), "+f"(d[18]), "+f"(d[19]), "+f"(d[20]), "+f"(d[21]), "+f"(d[22]), "+f"(d[23]), "+f"(d[24]), "+f"(d[25]), "+f"(d[26]), "+f"(d[27]), "+f"(d[28]), "+f"(d[29]), "+f"(d[30]), "+f"(d[31]), "+f"(d[32]), "+f"(d[33]), "+f"(d[34]), "+f"(d[35]), "+f"(d[36]), "+f"(d[37]), "+f"(d[38]), "+f"(d[39]), "+f"(d[40]), "+f"(d[41]), "+f"(d[42]), "+f"(d[43]), "+f"(d[44]), "+f"(d[45]), "+f"(d[46]), "+f"(d[47]), "+f"(d[48]), "+f"(d[49]), "+f"(d[50]), "+f"(d[51]), "+f"(d[52]), "+f"(d[53]), "+f"(d[54]), "+f"(d[55]), "+f"(d[56]), "+f"(d[57]), "+f"(d[58]), "+f"(d[59]), "+f"(d[60]), "+f"(d[61]), "+f"(d[62]), "+f"(d[63]), "+f"(d[64]), "+f"(d[65]), "+f"(d[66]), "+f"(d[67]), "+f"(d[68]), "+f"(d[69]), "+f"(d[70]), "+f"(d[71]), "+f"(d[72]), "+f"(d[73]), "+f"(d[74]), "+f"(d[75]), "+f"(d[76]), "+f"(d[77]), "+f"(d[78]), "+f"(d[79]), "+f"(d[80]), "+f"(d[81]), "+f"(d[82]), "+f"(d[83]), "+f"(d[84]), "+f"(d[85]), "+f"(d[86]), "+f"(d[87]), "+f"(d[88]), "+f"(d[89]), "+f"(d[90]), "+f"(d[91]) : "l"(da), "l"(db), "r"(sd), "n"(TB));
  }
};

constexpr uint32_t SMEM_BASE = 1024;
constexpr uint32_t OFF_XW   = 0;
constexpr uint32_t OFF_POOL = 57344;
constexpr uint32_t SLOT     = 16384;
constexpr uint32_t OFF_XE   = 139264;
constexpr uint32_t OFF_KV   = 131072;
constexpr uint32_t OFF_STG  = 196608;
constexpr uint32_t OFF_BAR  = 229376;
constexpr uint32_t SMEM_BYTES = OFF_BAR + 1088;

enum { B_X = 0, B_FULL = 7, B_KV = 56, B_EMPTY = 60, B_DFULL = 109, B_XR = 116, B_KVST = 123, B_DEMPTY = 125, B_ATT = 127, B_A5 = 128,
       B_DGO = 129, B_T5 = 130, B_DONE = 131, NBAR = 132 };

struct alignas(64) Params {
  const char* pf[5];
  const __nv_bfloat16* gate_w;
  uint4* outp;
  uint32_t* sync;
  char* kv;
  CUtensorMap x, wqkv, w1[2], wh[2], wd, wo, out;
};

__device__ __align__(1024) __nv_bfloat16 g_kv[(8 * 32 + 1) * 8192];
__device__ __align__(128) uint32_t g_sync[128 * 32 + 16 * 32 + 128];

constexpr int SPIN_LIMIT = 1 << 20;

__device__ __forceinline__ uint32_t s2u(const void* p) { return (uint32_t)__cvta_generic_to_shared(p); }
__device__ __forceinline__ void mbar_init(uint32_t b, uint32_t c) { asm volatile("mbarrier.init.shared::cta.b64 [%0], %1;" ::"r"(b), "r"(c) : "memory"); }
__device__ __forceinline__ void mbar_expect(uint32_t b, uint32_t tx) { asm volatile("mbarrier.arrive.expect_tx.shared::cta.b64 _, [%0], %1;" ::"r"(b), "r"(tx) : "memory"); }
__device__ __forceinline__ void mbar_arrive(uint32_t b) { asm volatile("mbarrier.arrive.shared::cta.b64 _, [%0];" ::"r"(b) : "memory"); }
__device__ __forceinline__ void mbar_wait(uint32_t b) {
  asm volatile("{\n.reg .pred p;\nWAIT_%=:\nmbarrier.try_wait.parity.shared::cta.b64 p, [%0], 0;\n@!p bra WAIT_%=;\n}" ::"r"(b) : "memory");
}
__device__ __forceinline__ void mbar_sleep(uint32_t b) {
  asm volatile("{\n.reg .pred p;\nWAIT_%=:\nmbarrier.try_wait.parity.shared::cta.b64 p, [%0], 0, 4000;\n@!p bra WAIT_%=;\n}" ::"r"(b) : "memory");
}
__device__ __forceinline__ void mbar_wait_block(uint32_t b) {
  uint32_t ok;
  int it = 0;
  do {
    asm volatile("{\n.reg .pred p;\nmbarrier.try_wait.parity.shared::cta.b64 p, [%1], 0;\nselp.u32 %0, 1, 0, p;\n}" : "=r"(ok) : "r"(b) : "memory");
  } while (!ok && ++it < (1 << 30));
}
__device__ __forceinline__ void mbar_wait_bounded(uint32_t b) {
  uint32_t ok;
  int it = 0;
  do {
    asm volatile("{\n.reg .pred p;\nmbarrier.try_wait.parity.shared::cta.b64 p, [%1], 0, 4000;\nselp.u32 %0, 1, 0, p;\n}" : "=r"(ok) : "r"(b) : "memory");
    if (++it > SPIN_LIMIT) __trap();
  } while (!ok);
}
#define ELECT_BEGIN "{\n.reg .pred p;\nelect.sync _|p, 0xffffffff;\n@p "
__device__ __forceinline__ void tma2d(uint32_t dst, const CUtensorMap* m, int c0, int c1, uint32_t bar) {
  asm volatile(ELECT_BEGIN "cp.async.bulk.tensor.2d.shared::cluster.global.mbarrier::complete_tx::bytes [%0], [%1, {%3, %4}], [%2];\n}"
               ::"r"(dst), "l"(m), "r"(bar), "r"(c0), "r"(c1) : "memory");
}
__device__ __forceinline__ void tma2d_mc(uint32_t dst, const CUtensorMap* m, int c0, int c1, uint32_t bar) {
  asm volatile(ELECT_BEGIN "cp.async.bulk.tensor.2d.shared::cluster.global.mbarrier::complete_tx::bytes.multicast::cluster [%0], [%1, {%3, %4}], [%2], %5;\n}"
               ::"r"(dst), "l"(m), "r"(bar), "r"(c0), "r"(c1), "h"((uint16_t)3) : "memory");
}
__device__ __forceinline__ void tma3d_mc(uint32_t dst, const CUtensorMap* m, int c0, int c1, int c2, uint32_t bar) {
  asm volatile(ELECT_BEGIN "cp.async.bulk.tensor.3d.shared::cluster.global.mbarrier::complete_tx::bytes.multicast::cluster [%0], [%1, {%3, %4, %5}], [%2], %6;\n}"
               ::"r"(dst), "l"(m), "r"(bar), "r"(c0), "r"(c1), "r"(c2), "h"((uint16_t)3) : "memory");
}
__device__ __forceinline__ void tma2d_add(const CUtensorMap* m, uint32_t src, int c0, int c1) {
  asm volatile(ELECT_BEGIN "cp.reduce.async.bulk.tensor.2d.global.shared::cta.add.tile.bulk_group [%0, {%2, %3}], [%1];\ncp.async.bulk.commit_group;\n}"
               ::"l"(m), "r"(src), "r"(c0), "r"(c1) : "memory");
}
__device__ __forceinline__ void prefetch_l2(const char* a, uint32_t bytes) {
  asm volatile("cp.async.bulk.prefetch.L2.global [%0], %1;" ::"l"(a), "r"(bytes) : "memory");
}
__device__ __forceinline__ void prefetch_map(const CUtensorMap* m) { asm volatile("prefetch.tensormap [%0];" ::"l"(m) : "memory"); }
__device__ __forceinline__ void wg_fence() { asm volatile("wgmma.fence.sync.aligned;" ::: "memory"); }
__device__ __forceinline__ void wg_commit() { asm volatile("wgmma.commit_group.sync.aligned;" ::: "memory"); }
template <int N> __device__ __forceinline__ void wg_wait() { asm volatile("wgmma.wait_group.sync.aligned %0;" ::"n"(N) : "memory"); }
constexpr uint32_t DHI128 = (1024u >> 4) | (1u << 30);
constexpr uint32_t DHI64  = (512u >> 4) | (2u << 30);
__device__ __forceinline__ constexpr uint32_t LBO(uint32_t bytes) { return (bytes >> 4) << 16; }
__device__ __forceinline__ uint64_t mkd(uint32_t lo, uint32_t hi) { return ((uint64_t)hi << 32) | lo; }
__device__ __forceinline__ uint32_t pack2(float lo, float hi) {
  uint32_t r;
  asm("cvt.rn.bf16x2.f32 %0, %1, %2;" : "=r"(r) : "f"(hi), "f"(lo));
  return r;
}
__device__ __forceinline__ float ex2(float x) { float y; asm("ex2.approx.ftz.f32 %0, %1;" : "=f"(y) : "f"(x)); return y; }
__device__ __forceinline__ float rcp(float x) { float y; asm("rcp.approx.ftz.f32 %0, %1;" : "=f"(y) : "f"(x)); return y; }
__device__ __forceinline__ float tanh_fast(float x) { float y; asm("tanh.approx.f32 %0, %1;" : "=f"(y) : "f"(x)); return y; }
__device__ __forceinline__ void stsm4(uint32_t a, uint32_t r0, uint32_t r1, uint32_t r2, uint32_t r3) {
  asm volatile("stmatrix.sync.aligned.m8n8.x4.shared.b16 [%0], {%1, %2, %3, %4};" ::"r"(a), "r"(r0), "r"(r1), "r"(r2), "r"(r3) : "memory");
}
__device__ __forceinline__ uint32_t ld_acquire(const uint32_t* p) {
  uint32_t v;
  asm volatile("ld.acquire.gpu.global.u32 %0, [%1];" : "=r"(v) : "l"(p) : "memory");
  return v;
}
__device__ __forceinline__ void st_release(uint32_t* p, uint32_t v) { asm volatile("st.release.gpu.global.u32 [%0], %1;" ::"l"(p), "r"(v) : "memory"); }
__device__ __forceinline__ void flag_wait(const uint32_t* p, uint32_t v) {
  while (ld_acquire(p) != v) __nanosleep(100);
}
__device__ __forceinline__ float glu(float g2, float u2) { return fmaf(tanh_fast(g2), u2, u2); }

__device__ __forceinline__ uint32_t d_slot(int t) {
  const int k = t >= 5 ? t - 5 : t;
  return k == 0 ? 176128u : (k == 4 ? 139264u : (k - 1) * 36864u);
}
__device__ __forceinline__ uint32_t next_slot(int s, uint32_t off) {
  if (s == 4) return OFF_STG;
  if (s == 6 || off == OFF_POOL + 4 * SLOT) return OFF_POOL;
  return off + SLOT;
}
__device__ __forceinline__ uint32_t ld_relaxed(const char* p) {
  uint32_t v;
  asm volatile("ld.relaxed.gpu.global.u32 %0, [%1];" : "=r"(v) : "l"(p) : "memory");
  return v;
}
__device__ __forceinline__ float bf_lo(uint32_t v) { return __uint_as_float(v << 16); }
__device__ __forceinline__ float bf_hi(uint32_t v) { return __uint_as_float(v & 0xffff0000u); }

__global__ void __cluster_dims__(2, 1, 1) __launch_bounds__(384, 1)
fused_kernel(const __grid_constant__ Params p) {
  extern __shared__ __align__(1024) char smem_raw[];
  const uint32_t sb = s2u(smem_raw);
  const uint32_t bar = sb + OFF_BAR;
  const int lane = threadIdx.x & 31;
  const int warp = __shfl_sync(0xffffffffu, threadIdx.x >> 5, 0);
  const int rank = blockIdx.x & 1, j = blockIdx.x >> 4, m = blockIdx.x & 15;
  unsigned short gv[14];
  if (warp < 7) {
    if (lane == 0) {
      mbar_init(bar + 8 * (B_X + warp), 1); mbar_init(bar + 8 * (B_FULL + warp), 2); mbar_init(bar + 8 * (B_EMPTY + warp), 4);
      mbar_expect(bar + 8 * (B_X + warp), 16384); mbar_expect(bar + 8 * (B_FULL + warp), 14848);
    }
    __syncwarp();
    if (warp == 0) {
      tma2d(sb + OFF_XW, &p.x, 0, m * 128, bar + 8 * B_X);
      tma2d(sb + OFF_XE, &p.x, 0, m * 128 + 64, bar + 8 * B_X);
    }
  } else if (warp == 10) {
    const unsigned short* gw = reinterpret_cast<const unsigned short*>(p.gate_w) + lane;
#pragma unroll
    for (int i = 0; i < 14; i++) gv[i] = __ldg(gw + 32 * i);
  } else if (lane == 0) {
    prefetch_map(warp == 8 ? &p.wqkv : &p.wh[rank]);
  }
  asm volatile("fence.mbarrier_init.release.cluster;" ::: "memory");
  __syncwarp();
  asm volatile("barrier.cluster.arrive.relaxed.aligned;" ::: "memory");
  const int odd = j & 1;
  const int fb = (7 * j + odd) >> 1;
  const int hc = 224 * j + (odd ? 0 : 192);
  uint32_t epoch;
  if (warp < 8) {
    if (lane == 0) {
      if (warp < 7) { mbar_init(bar + 8 * (B_FULL + 7 + warp), 2); mbar_expect(bar + 8 * (B_FULL + 7 + warp), 14848); }
      else { mbar_init(bar + 8 * B_DGO, 1); mbar_init(bar + 8 * B_T5, 2); mbar_init(bar + 8 * B_DONE, 8); }
    }
    asm volatile("fence.mbarrier_init.release.cluster;" ::: "memory");
    asm volatile("bar.sync 1, 256;" ::: "memory");
  }
  asm volatile("barrier.cluster.wait.acquire.aligned;" ::: "memory");

  if (warp >= 8) {
    asm volatile("setmaxnreg.dec.sync.aligned.u32 24;");
    if (warp == 8 || warp == 11) {
      const bool first = warp == 8;
      uint32_t off = OFF_POOL;
      int blk = fb, kc = 0;
#pragma unroll 1
      for (int s = 0; s < (first ? 49 : 14); s++) {
        if (s >= 7) mbar_wait(bar + 8 * (B_EMPTY + (s < 12 ? s - 7 : s - 5)));
        const uint32_t dst = sb + off, fbar = bar + 8 * (B_FULL + s);
        if (s >= 14) {
          tma2d_mc(dst + rank * 8192, &p.w1[rank], 64 * blk, 64 * kc, fbar);
          if (++kc == 7) { kc = 0; blk += s == 34 ? -1 : 1; }
        } else if (first) {
          tma3d_mc(dst + rank * 6144, &p.wqkv, 56 * j, 32 * s + 16 * rank, 0, fbar);
        } else {
          tma2d_mc(dst + 12288 + rank * 2048, &p.wh[rank], hc, 32 * s, fbar);
          if ((s & 1) && s < 12) {
            const int c = (s + 1) >> 1;
            tma2d(sb + OFF_XW + c * 8192, &p.x, 64 * c, m * 128, bar + 8 * (B_X + c));
            tma2d(sb + OFF_XE + c * 8192, &p.x, 64 * c, m * 128 + 64, bar + 8 * (B_X + c));
          }
        }
        off = next_slot(s, off);
      }
      if (!first) {
        mbar_sleep(bar + 8 * (B_EMPTY + 13));
#pragma unroll 1
        for (int c = 0; c < 7; c++) {
          mbar_sleep(bar + 8 * (B_EMPTY + 28 + c));
          tma2d(sb + OFF_XW + c * 8192, &p.x, 64 * c, m * 128 + 64, bar + 8 * (B_XR + c));
        }
      }
      int sl = j == 7 ? 3 : j;
#pragma unroll 1
      for (int t = 0; t < (first ? 0 : 7); t++) {
        if (t != 3) mbar_sleep(bar + 8 * (t == 0 ? B_A5 : (t < 3 ? B_EMPTY + 44 + 2 * t : (t == 4 ? B_ATT : B_DEMPTY + t - 5))));
        const uint32_t dst = sb + d_slot(t), fbar = bar + 8 * (B_DFULL + t);
        tma2d_mc(dst + rank * 14336, &p.wd, 64 * sl, 224 * j + 112 * rank, fbar);
        tma2d_mc(dst + 28672 + rank * 4096, &p.wo, 64 * sl, 56 * j + 32 * rank, fbar);
        sl = sl == 6 ? 0 : sl + 1;
      }
    } else if (warp == 9) {
      epoch = p.sync[4608 + blockIdx.x] + 1;
      if (lane == 0) { prefetch_map(&p.w1[rank]); prefetch_map(&p.wd); prefetch_map(&p.wo); prefetch_map(&p.out); }
#pragma unroll 1
      for (int c = 0; c < 7; c++) {
        mbar_sleep(bar + 8 * (B_EMPTY + c));
        const int pc = 2 * c + lane;
        if (lane < 2 && pc < 13) {
          const char* a = pc < 8 ? p.pf[1 + lane] + (size_t)blockIdx.x * 12544 + c * 3136
                                 : (pc < 12 ? p.pf[3] + (size_t)blockIdx.x * 12544 + (pc - 8) * 3136 : p.pf[4] + (size_t)blockIdx.x * 3136);
          prefetch_l2(a, 3136);
        }
        __syncwarp();
      }
      char* const kvj = p.kv + (size_t)j * (32 * 16384);
#pragma unroll 1
      for (int u = 1; u >= 0; u--) {
        mbar_wait(bar + 8 * (B_KVST + u));
        asm volatile(ELECT_BEGIN "cp.async.bulk.global.shared::cta.bulk_group [%0], [%1], 16384;\n}"
                     ::"l"(kvj + (2 * m + u) * 16384), "r"(sb + OFF_STG + u * 16384) : "memory");
        asm volatile("cp.async.bulk.commit_group;\ncp.async.bulk.wait_group 0;" ::: "memory");
        asm volatile("fence.proxy.async.global;" ::: "memory");
        __syncwarp();
        if (lane == 0) st_release(&p.sync[(m * 8 + j) * 32 + u], epoch);
      }
      if (lane == 0) mbar_arrive(bar + 8 * B_T5);
      if (lane < 8) flag_wait(&p.sync[4096 + m * 32 + lane], epoch);
      asm volatile("fence.proxy.async.global;" ::: "memory");
      __syncwarp();
      if (lane == 0) {
        mbar_arrive(bar + 8 * B_DGO);
        p.sync[4608 + blockIdx.x] = epoch;
      }
    } else {
      if ((sb & 0x3FFFF) != SMEM_BASE) __trap();
      const uint32_t ga = sb + OFF_POOL + (lane >> 4) * 6144 + (lane & 15) * 128 + ((7 ^ (lane & 7)) << 4);
#pragma unroll
      for (int s = 0; s < 7; s++) asm volatile("st.shared.u16 [%0], %1;" ::"r"(ga + (s < 5 ? s * SLOT : OFF_STG - OFF_POOL + (s - 5) * SLOT)), "h"(gv[s]) : "memory");
      asm volatile("fence.proxy.async.shared::cta;" ::: "memory");
      __syncwarp();
      if (lane < 7) mbar_arrive(bar + 8 * (B_FULL + lane));
#pragma unroll 1
      for (int s = 7; s < 14; s++) {
        mbar_wait_bounded(bar + 8 * (B_EMPTY + (s < 12 ? s - 7 : s - 5)));
        asm volatile("st.shared.u16 [%0], %1;" ::"r"(ga + (s < 12 ? s - 7 : s - 12) * SLOT), "h"(gv[7]) : "memory");
#pragma unroll
        for (int i = 7; i < 13; i++) gv[i] = gv[i + 1];
        asm volatile("fence.proxy.async.shared::cta;" ::: "memory");
        __syncwarp();
        if (lane == 0) mbar_arrive(bar + 8 * (B_FULL + s));
        uint4* dst = p.outp + (m * 8 + j) * 896 + (s - 7) * 128 + lane;
#pragma unroll
        for (int i = 0; i < 4; i++) dst[i * 32] = make_uint4(0, 0, 0, 0);
      }
      epoch = p.sync[4608 + blockIdx.x] + 1;
      __threadfence();
      __syncwarp();
      if (lane == 0) { st_release(&p.sync[4096 + m * 32 + j], epoch); }
      mbar_wait_bounded(bar + 8 * (B_EMPTY + 13));
      const char* const kvj = p.kv + (size_t)j * (32 * 16384);
#pragma unroll 1
      for (int u = 0; u < 4; u++) {
        const int t = (0x0213 >> (4 * u)) & 3, kb = 2 * m - 4 + t;
        if (kb >= 0) {
          const uint32_t* f = &p.sync[((kb >> 1) * 8 + j) * 32 + (t & 1)];
          for (int it = 0; ld_acquire(f) != epoch; it++) if (it > SPIN_LIMIT) __trap();
          asm volatile("fence.proxy.async.global;" ::: "memory");
        }
        mbar_wait_bounded(bar + 8 * (t ? B_EMPTY + 14 + 2 * t : B_T5));
        asm volatile(ELECT_BEGIN "cp.async.bulk.shared::cluster.global.mbarrier::complete_tx::bytes [%0], [%1], 16384, [%2];\n}"
                     ::"r"(sb + OFF_KV + (t ? t : 5) * 16384), "l"(kb >= 0 ? kvj + kb * 16384 : p.kv + 256 * 16384), "r"(bar + 8 * (B_KV + t)) : "memory");
      }
      mbar_wait_bounded(bar + 8 * B_DONE);
    }
  } else {
    asm volatile("setmaxnreg.inc.sync.aligned.u32 240;");
    const int g = warp >> 2, w = warp & 3, r = lane >> 2, q = lane & 3;
    const bool sig = lane == 0 && w < 2;
    uint32_t sigbar;
    asm("mapa.shared::cluster.u32 %0, %1, %2;" : "=r"(sigbar) : "r"(bar), "r"(rank ^ (w & 1)));
    auto release = [&](int b) { if (sig) asm volatile("mbarrier.arrive.shared::cluster.b64 _, [%0];" ::"r"(sigbar + 8 * b) : "memory"); };
    constexpr uint32_t db = SMEM_BASE >> 4;
    uint32_t xd = db + ((g ? OFF_XE : OFF_XW) >> 4) + LBO(16);
    const uint32_t hpark = sb + OFF_XE + (threadIdx.x & 127) * 16;
    uint32_t of[4][4];
    float acc[2][32];
    uint32_t hf[14][4];
    uint32_t qp[7][2];
    float c0, c1;
    float e0, e1;
    const uint32_t hb0 = odd * 256 + (g ? 0 : 1024), hb1 = odd * 256 - (g ? 0 : 512);
    auto down_a = [&](float (&acc)[32], uint32_t st) {
#pragma unroll
      for (int i = 0; i < 6; i++) {
        const uint64_t d = mkd(st + (i < 4 ? hb0 : hb1) + i * 128, DHI128);
        if (i == 0) WG<64>::rsz<1>(acc, hf[i][0], hf[i][1], hf[i][2], hf[i][3], d);
        else WG<64>::rs<1>(acc, hf[i][0], hf[i][1], hf[i][2], hf[i][3], d, 1);
      }
      wg_commit();
    };
    auto down_b = [&](float (&acc)[32], uint32_t st) {
#pragma unroll
      for (int i = 6; i < 14; i++)
        WG<64>::rs<1>(acc, hf[i][0], hf[i][1], hf[i][2], hf[i][3], mkd(i < 12 ? st + hb1 + i * 128 : st + (odd ? 0 : 1536) + (i - 12) * 128, DHI128), 1);
#pragma unroll
      for (int i = 0; i < 4; i++) WG<64>::rs<1>(acc, of[i][0], of[i][1], of[i][2], of[i][3], mkd(st + 1792 + i * 128, DHI128), 1);
      wg_commit();
    };

    {
      float aq[92], ah[32], ga[64], gb[64];
      uint32_t off = OFF_POOL;
      constexpr unsigned long long FIRSTS = (unsigned long long)B_KVST | (unsigned long long)(B_FULL + 14) << 8 | (unsigned long long)(B_FULL + 27) << 16 |
          (unsigned long long)(B_FULL + 40) << 24 | (unsigned long long)B_DFULL << 32 | (unsigned long long)(B_EMPTY + 7) << 40 |
          (unsigned long long)(B_EMPTY + 21) << 48 | (unsigned long long)(B_EMPTY + 35) << 56;
      const uint32_t ib = bar + 8 * ((int)(FIRSTS >> (8 * warp)) & 255);
      const int in = (0xEEEEDDD6u >> (4 * warp)) & 15;
      const uint32_t icnt = (0x22411114u >> (4 * warp)) & 15;
#pragma unroll 1
      for (int s = 0; s < 14; s++) {
        if ((s & 1) == 0) mbar_wait(bar + 8 * (B_X + (s >> 1)));
        mbar_wait(bar + 8 * (B_FULL + s));
        const uint32_t xa = xd + (s >> 1) * 512 + (s & 1) * 4, st = db + (off >> 4);
        wg_fence();
#pragma unroll
        for (int kk = 0; kk < 2; kk++) {
          const uint64_t da = mkd(xa + kk * 2, DHI128);
          WG<184>::ss<1>(aq, da, mkd(st + kk * 384 + LBO(2048), DHI128), s | kk);
          WG<64>::ss<1>(ah, da, mkd(st + 768 + kk * 64 + LBO(2048), DHI64), s | kk);
        }
        wg_commit();
        if (lane == 0 && s < in) {
          mbar_init(ib + 8 * s, icnt);
          if (icnt == 1) mbar_expect(ib + 8 * s, warp < 4 ? 16384 : (s < 7 ? 36864 : 8192));
          asm volatile("fence.mbarrier_init.release.cluster;" ::: "memory");
        }
        __syncwarp();
        off = next_slot(s, off);
        if (s > 0) { wg_wait<1>(); release(B_EMPTY + s - 1); }
      }
      int s = 14;
      auto issue = [&](float (&acc)[64], int kc, bool first, bool defer = false) {
        mbar_wait(bar + 8 * (B_FULL + s));
        const uint32_t sw_ = db + (off >> 4) + LBO(8192), xa = xd + kc * 512;
        wg_fence();
#pragma unroll
        for (int kk = 0; kk < 4; kk++) {
          if (first && kk == 0) WG<128>::ssz<1>(acc, mkd(xa, DHI128), mkd(sw_, DHI128));
          else WG<128>::ss<1>(acc, mkd(xa + kk * 2, DHI128), mkd(sw_ + kk * 128, DHI128), 1);
        }
        wg_commit();
        off = next_slot(s, off);
        if (defer) return;
        wg_wait<1>();
        release(B_EMPTY + s - 1);
        s++;
      };
      auto glu_part = [&](float (&acc)[64], int blk, int i0, int i1) {
#pragma unroll
        for (int i = i0; i < i1; i++) {
          const float e = (i & 1) ? e1 : e0;
          asm volatile("" : "+f"(acc[2 * i]), "+f"(acc[2 * i + 1]), "+f"(acc[32 + 2 * i]), "+f"(acc[33 + 2 * i]));
          hf[4 * blk + (i >> 2)][i & 3] = pack2(glu(0.5f * acc[2 * i], acc[32 + 2 * i] * e), glu(0.5f * acc[2 * i + 1], acc[33 + 2 * i] * e));
          asm volatile("" : "+r"(hf[4 * blk + (i >> 2)][i & 3]));
        }
      };
      auto solo = [&](float (&acc)[64], int kc, bool first, bool rel, float (&prev)[64], int blk, int part) {
        mbar_wait(bar + 8 * (B_FULL + s));
        const uint32_t sw_ = db + (off >> 4) + LBO(8192), xa = xd + kc * 512;
#pragma unroll
        for (int hh = 0; hh < 2; hh++) {
          wg_fence();
#pragma unroll
          for (int kk = 2 * hh; kk < 2 * hh + 2; kk++) {
            if (first && kk == 0) WG<128>::ssz<1>(acc, mkd(xa, DHI128), mkd(sw_, DHI128));
            else WG<128>::ss<1>(acc, mkd(xa + kk * 2, DHI128), mkd(sw_ + kk * 128, DHI128), 1);
          }
          wg_commit();
          if (part >= 0) glu_part(prev, blk, 8 * part + 4 * hh, 8 * part + 4 * hh + 4);
          wg_wait<1>();
          if (hh == 0 && rel) release(B_EMPTY + s - 1);
        }
        off = next_slot(s, off);
        s++;
      };
      auto retire = [&]() {
        wg_wait<1>();
        release(B_EMPTY + s - 1);
        s++;
      };
      issue(ga, 0, true);
      {
#pragma unroll
        for (int i = 0; i < 92; i++) asm volatile("" : "+f"(aq[i]));
        mbar_wait(bar + 8 * (B_EMPTY + 6));
        const int row = 16 * w + (lane & 15);
        const uint32_t base = sb + OFF_STG + g * 16384 + row * 128;
        const int hi = lane >> 4, sw = lane & 7;
        const uint32_t v30 = pack2(aq[76], aq[77]), v31 = pack2(aq[78], aq[79]), one = 0x3f803f80u;
#pragma unroll
        for (int nb = 0; nb < 8; nb += 2) {
          const uint32_t o = base + (((nb + hi) ^ sw) << 4);
          const float* a = &aq[32 + 4 * nb];
          stsm4(o, pack2(a[0], a[1]), pack2(a[2], a[3]), pack2(a[4], a[5]), pack2(a[6], a[7]));
          const float* v = &aq[64 + 4 * (nb < 4 ? nb : nb - 1)];
          if (nb == 2) stsm4(o + 8192, pack2(v[0], v[1]), pack2(v[2], v[3]), q < 2 ? v30 : one, q < 2 ? v31 : one);
          else if (nb == 4) stsm4(o + 8192, q < 2 ? one : v30, q < 2 ? one : v31, pack2(v[4], v[5]), pack2(v[6], v[7]));
          else stsm4(o + 8192, pack2(v[0], v[1]), pack2(v[2], v[3]), pack2(v[4], v[5]), pack2(v[6], v[7]));
        }
      }
      asm volatile("fence.proxy.async.shared::cta;" ::: "memory");
      __syncwarp();
      if (lane == 0) mbar_arrive(bar + 8 * (B_KVST + g));
      issue(ga, 1, false, true);
      retire();
      issue(ga, 2, false, true);
#pragma unroll
      for (int nb = 0; nb < 7; nb++) {
        const float cs = 0.18898223650461362f * 1.4426950408889634f;
        qp[nb][0] = pack2(aq[4 * nb] * cs, aq[4 * nb + 1] * cs); qp[nb][1] = pack2(aq[4 * nb + 2] * cs, aq[4 * nb + 3] * cs);
      }
      c0 = rcp(1.f + ex2(-1.4426950408889634f * __shfl_sync(0xffffffffu, aq[28], lane & 28)));
      c1 = rcp(1.f + ex2(-1.4426950408889634f * __shfl_sync(0xffffffffu, aq[30], lane & 28)));
      e0 = 0.5f - 0.5f * c0; e1 = 0.5f - 0.5f * c1;
#pragma unroll
      for (int i = 0; i < 8; i++) {
        const float e = (i & 1) ? e1 : e0;
        asm volatile("" : "+f"(ah[2 * i]), "+f"(ah[2 * i + 1]), "+f"(ah[16 + 2 * i]), "+f"(ah[17 + 2 * i]));
        hf[12 + (i >> 2)][i & 3] = pack2(glu(0.5f * ah[2 * i], ah[16 + 2 * i] * e), glu(0.5f * ah[2 * i + 1], ah[17 + 2 * i] * e));
      }
      retire();
#pragma unroll 1
      for (int kc = 3; kc < 7; kc++) issue(ga, kc, false);
      wg_wait<0>();
      release(B_EMPTY + 20);
      if (g == 0) {
        solo(gb, 0, true, false, ga, 1, 0);
        solo(gb, 1, false, true, ga, 1, 1);
#pragma unroll 1
        for (int kc = 2; kc < 7; kc++) solo(gb, kc, false, true, ga, 0, -1);
        solo(ga, 0, true, true, gb, 0, -1);
        solo(ga, 1, false, true, gb, 2, 0);
        solo(ga, 2, false, true, gb, 2, 1);
#pragma unroll 1
        for (int kc = 3; kc < 7; kc++) solo(ga, kc, false, true, gb, 0, -1);
        mbar_wait(bar + 8 * (B_EMPTY + 14));
#pragma unroll
        for (int i = 8; i < 12; i++)
          asm volatile("st.shared.v4.u32 [%0], {%1, %2, %3, %4};" ::"r"(hpark + (i - 8) * 2048), "r"(hf[i][0]), "r"(hf[i][1]), "r"(hf[i][2]), "r"(hf[i][3]) : "memory");
        wg_wait<0>();
        release(B_EMPTY + 34);
        mbar_wait(bar + 8 * B_T5);
      }
      mbar_wait_block(bar + 8 * (B_KVST + g));
      int dd = 16 * (16 * w + r - 2 * q + 1);
      const uint32_t qh[2][8] = {{qp[0][0], qp[0][1], qp[1][0], qp[1][1], qp[2][0], qp[2][1], q < 2 ? qp[3][0] : 0u, q < 2 ? qp[3][1] : 0u},
                                 {q < 2 ? 0u : qp[3][0], q < 2 ? 0u : qp[3][1], qp[4][0], qp[4][1], qp[5][0], qp[5][1], qp[6][0], qp[6][1]}};
      float O[2][16], S[2][32];
      const uint32_t tk = db + ((OFF_KV + g * 16384) >> 4), tx0 = g ? tk : tk + 5120;
      auto tile = [&](int i) { return i == 3 ? tx0 : tk + 1024 * (i == 4 ? 1 : 4 - i); };
      auto scores = [&](int n) {
        const int h = n & 1;
        const uint32_t t = tile(n >> 1) + 3 * h + LBO(16);
        WG<64>::rsz<0>(S[h], qh[h][0], qh[h][1], qh[h][2], qh[h][3], mkd(t, DHI128));
        WG<64>::rs<0>(S[h], qh[h][4], qh[h][5], qh[h][6], qh[h][7], mkd(t + 2, DHI128), 1);
      };
      wg_fence();
      scores(0);
      scores(1);
      wg_commit();
      glu_part(ga, 0, 0, 16);
#pragma unroll 1
      do { wg_wait<0>(); } while (blockIdx.y == 1);
#pragma unroll
      for (int n = 0; n < 10; n++) {
        const int h = n & 1;
        uint32_t P[16];
        if (n == 6) asm volatile("" : "+r"(dd));
#pragma unroll
        for (int e = 0; e < 32; e++) asm volatile("" : "+f"(S[h][e]));
#pragma unroll
        for (int e = 0; e < 16; e++) {
          P[e] = pack2(ex2(S[h][2 * e]), ex2(S[h][2 * e + 1]));
          if (n < 2 || (n >> 1) == 3) {
            const int cst = 8 * (e >> 1) - 8 * (e & 1);
            uint32_t later;
            asm("shl.b32 %0, %1, %2;" : "=r"(later) : "r"(0xffffffffu), "r"(max(dd - 16 * cst, 0)));
            P[e] &= n < 2 ? ~later : later;
          }
          asm volatile("" : "+r"(P[e]));
        }
        if (h == 0 && n < 8) mbar_wait(bar + 8 * (n == 0 && g ? B_KVST : B_KV + g + (n == 4 ? 0 : (n == 6 ? 1 : 3 - (n >> 1)))));
        wg_fence();
        if (n == 0) wg_wait<0>(); else wg_wait<1>();
        if (n < 8) { scores(n + 2); wg_commit(); }
#pragma unroll
        for (int kk = 0; kk < 4; kk++) {
          const uint64_t d = mkd(tile(n >> 1) + 4 * h + 512 + kk * 128 + LBO(8192), DHI128);
          if (n < 2 && kk == 0) WG<32>::rsz<1>(O[h], P[0], P[1], P[2], P[3], d);
          else WG<32>::rs<1>(O[h], P[4 * kk], P[4 * kk + 1], P[4 * kk + 2], P[4 * kk + 3], d, 1);
        }
        wg_commit();
        if (n == 3 && threadIdx.x == 128) mbar_arrive(bar + 8 * B_T5);
        if (n == 7 && g == 0) release(B_A5);
      }
      wg_wait<0>();
      if (g == 1) { release(B_A5); release(B_ATT); }
#pragma unroll
      for (int e = 0; e < 16; e++) asm volatile("" : "+f"(O[0][e]), "+f"(O[1][e]));
      {
        const float la = q < 2 ? O[1][0] : O[0][12], lb = q < 2 ? O[1][2] : O[0][14];
        float z0 = 0.f, z1 = 0.f;
#pragma unroll
        for (int e = 0; e < 16; e += 2) { z0 = fmaf(O[0][e], O[1][e], z0); z1 = fmaf(O[0][e + 1], O[1][e + 1], z1); }
        const bool ok = fminf(la, lb) >= 0x1p-40f && fmaxf(la, lb) <= 0x1p64f && fabsf(z0 + z1) < INFINITY;
        if (!__all_sync(0xffffffffu, ok)) {
          mbar_wait(bar + 8 * B_T5);
          const char* const kvj = p.kv + (size_t)j * (32 * 16384) + q * 4;
          float mx[4] = {-INFINITY, -INFINITY, -INFINITY, -INFINITY};
#pragma unroll
          for (int e = 0; e < 16; e++) { O[0][e] = 0.f; O[1][e] = 0.f; }
#pragma unroll 1
          for (int d = 0; d < 256; d++) {
#pragma unroll
            for (int hr = 0; hr < 4; hr++) {
              const int h = hr >> 1, up = hr & 1;
              const int key = m * 128 + warp * 16 + r + 8 * up - d, kc = max(key, 0);
              const char* row = kvj + (kc >> 6) * 16384 + (kc & 63) * 128;
              float sc = 0.f;
#pragma unroll
              for (int b = 0; b < 4; b++) {
                const uint32_t kw = ld_relaxed(row + (((3 * h + b) ^ (kc & 7)) << 4)), qw = qh[h][2 * b + up];
                sc = fmaf(bf_lo(qw), bf_lo(kw), fmaf(bf_hi(qw), bf_hi(kw), sc));
              }
              sc += __shfl_xor_sync(0xffffffffu, sc, 1);
              sc += __shfl_xor_sync(0xffffffffu, sc, 2);
              if (key < 0) sc = -INFINITY;
              const float mn = fmaxf(mx[hr], sc), al = ex2(mx[hr] - mn), pr = ex2(sc - mn);
              mx[hr] = mn;
#pragma unroll
              for (int b = 0; b < 4; b++) {
                const uint32_t vw = ld_relaxed(row + 8192 + (((4 * h + b) ^ (kc & 7)) << 4));
                O[h][4 * b + 2 * up] = fmaf(pr, bf_lo(vw), O[h][4 * b + 2 * up] * al);
                O[h][4 * b + 2 * up + 1] = fmaf(pr, bf_hi(vw), O[h][4 * b + 2 * up + 1] * al);
              }
            }
          }
        }
      }
      const float s0 = c0 * rcp(__shfl_sync(0xffffffffu, O[0][12], lane | 2)), s1 = c1 * rcp(__shfl_sync(0xffffffffu, O[0][14], lane | 2));
      const float u0 = c0 * rcp(__shfl_sync(0xffffffffu, O[1][0], lane & 29)), u1 = c1 * rcp(__shfl_sync(0xffffffffu, O[1][2], lane & 29));
      of[0][0] = pack2(O[0][0] * s0, O[0][1] * s0);   of[0][1] = pack2(O[0][2] * s1, O[0][3] * s1);
      of[0][2] = pack2(O[0][4] * s0, O[0][5] * s0);   of[0][3] = pack2(O[0][6] * s1, O[0][7] * s1);
      of[1][0] = pack2(O[0][8] * s0, O[0][9] * s0);   of[1][1] = pack2(O[0][10] * s1, O[0][11] * s1);
      of[1][2] = q < 2 ? pack2(O[0][12] * s0, O[0][13] * s0) : pack2(O[1][0] * u0, O[1][1] * u0);
      of[1][3] = q < 2 ? pack2(O[0][14] * s1, O[0][15] * s1) : pack2(O[1][2] * u1, O[1][3] * u1);
      of[2][0] = pack2(O[1][4] * u0, O[1][5] * u0);   of[2][1] = pack2(O[1][6] * u1, O[1][7] * u1);
      of[2][2] = pack2(O[1][8] * u0, O[1][9] * u0);   of[2][3] = pack2(O[1][10] * u1, O[1][11] * u1);
      of[3][0] = pack2(O[1][12] * u0, O[1][13] * u0); of[3][1] = pack2(O[1][14] * u1, O[1][15] * u1);
      of[3][2] = 0u; of[3][3] = 0u;
      if (g == 1) {
        s = 35;
        off = OFF_POOL + 3 * SLOT;
        xd = db + (OFF_XW >> 4) + LBO(16);
        mbar_wait(bar + 8 * B_XR);
        solo(ga, 0, true, false, gb, 0, -1);
#pragma unroll 1
        for (int kc = 1; kc < 7; kc++) { mbar_wait(bar + 8 * (B_XR + kc)); solo(ga, kc, false, true, gb, 0, -1); }
        solo(gb, 0, true, true, ga, 0, -1);
        solo(gb, 1, false, true, ga, 1, 0);
        solo(gb, 2, false, true, ga, 1, 1);
#pragma unroll 1
        for (int kc = 3; kc < 7; kc++) solo(gb, kc, false, true, ga, 0, -1);
        wg_wait<0>();
        release(B_EMPTY + 48);
        mbar_wait(bar + 8 * B_DFULL);
        wg_fence();
        down_a(acc[0], db + (d_slot(0) >> 4) + LBO(8192));
        glu_part(gb, 2, 0, 16);
      } else {
#pragma unroll
        for (int i = 8; i < 12; i++)
          asm volatile("ld.shared.v4.u32 {%0, %1, %2, %3}, [%4];" : "=r"(hf[i][0]), "=r"(hf[i][1]), "=r"(hf[i][2]), "=r"(hf[i][3]) : "r"(hpark + (i - 8) * 2048) : "memory");
        asm volatile("bar.sync 2, 128;" ::: "memory");
        release(B_ATT);
        mbar_wait(bar + 8 * B_DFULL);
        wg_fence();
        down_a(acc[0], db + (d_slot(0) >> 4) + LBO(8192));
      }
    }
    {
      uint32_t v[16];
      int sl = j == 7 ? 3 : j;
      const uint32_t sg = sb + (g ? OFF_POOL + 4 * SLOT : OFF_STG + SLOT) + w * 2048;
      const uint32_t so = (lane & 15) * 128, sx = ((lane >> 4) ^ (lane & 7)) << 4;
      auto send = [&](int t) {
        const uint32_t ob = sg + (t & 1) * 8192;
        asm volatile("cp.async.bulk.wait_group.read 1;" ::: "memory");
        __syncwarp();
#pragma unroll
        for (int i = 0; i < 4; i++) stsm4(ob + so + (sx ^ (i << 5)), v[4 * i], v[4 * i + 1], v[4 * i + 2], v[4 * i + 3]);
        asm volatile("fence.proxy.async.shared::cta;" ::: "memory");
        __syncwarp();
        tma2d_add(&p.out, ob, 64 * sl, m * 128 + warp * 16);
        sl = sl == 6 ? 0 : sl + 1;
      };
#pragma unroll
      for (int t = 0; t < 7; t++) {
        wg_fence();
        down_b(acc[t & 1], db + (d_slot(t) >> 4) + LBO(8192));
        if (t == 6) break;
        mbar_wait(bar + 8 * (B_DFULL + t + 1));
        if (t == 5 && lane == 0) mbar_arrive(bar + 8 * B_DONE);
        wg_fence();
        down_a(acc[(t + 1) & 1], db + (d_slot(t + 1) >> 4) + LBO(8192));
        wg_wait<1>();
#pragma unroll
        for (int i = 0; i < 16; i++) { asm volatile("" : "+f"(acc[t & 1][2 * i]), "+f"(acc[t & 1][2 * i + 1])); v[i] = pack2(acc[t & 1][2 * i], acc[t & 1][2 * i + 1]); }
        if (t < 2) release(B_DEMPTY + t);
        if (t == 0) {
          mbar_wait(bar + 8 * B_DGO);
          asm volatile("fence.proxy.async.global;" ::: "memory");
        }
        send(t);
      }
      wg_wait<0>();
#pragma unroll
      for (int i = 0; i < 16; i++) v[i] = pack2(acc[0][2 * i], acc[0][2 * i + 1]);
      send(6);
      asm volatile("cp.async.bulk.wait_group.read 0;" ::: "memory");
    }
  }
}

typedef CUresult (*EncodeFn)(CUtensorMap*, CUtensorMapDataType, cuuint32_t, void*, const cuuint64_t*, const cuuint64_t*, const cuuint32_t*,
                             const cuuint32_t*, CUtensorMapInterleave, CUtensorMapSwizzle, CUtensorMapL2promotion, CUtensorMapFloatOOBfill);

void make_map(EncodeFn enc, CUtensorMap* m, const void* base, int rank, uint64_t d0, uint64_t d1, uint64_t d2, uint64_t s1, uint64_t s2,
              uint32_t b0, uint32_t b1, uint32_t b2, CUtensorMapSwizzle sw) {
  cuuint64_t gd[3] = {d0, d1, d2};
  cuuint64_t gs[2] = {s1, s2};
  cuuint32_t bd[3] = {b0, b1, b2};
  cuuint32_t es[3] = {1, 1, 1};
  enc(m, CU_TENSOR_MAP_DATA_TYPE_BFLOAT16, rank, const_cast<void*>(base), gd, gs, bd, es, CU_TENSOR_MAP_INTERLEAVE_NONE, sw,
      CU_TENSOR_MAP_L2_PROMOTION_L2_128B, CU_TENSOR_MAP_FLOAT_OOB_FILL_NONE);
}

}

extern "C" void kernel_launch(void* const* d_in, const int* in_sizes, int n_in, void* d_out, int out_size) {
  (void)in_sizes; (void)n_in; (void)out_size;
  void* fn = nullptr;
  cudaDriverEntryPointQueryResult qr;
  cudaGetDriverEntryPoint("cuTensorMapEncodeTiled", &fn, cudaEnableDefault, &qr);
  EncodeFn enc = (EncodeFn)fn;
  void* kv = nullptr;
  void* sync = nullptr;
  cudaGetSymbolAddress(&kv, g_kv);
  cudaGetSymbolAddress(&sync, g_sync);
  cudaFuncSetAttribute(fused_kernel, cudaFuncAttributeMaxDynamicSharedMemorySize, SMEM_BYTES);

  const void *x = d_in[0], *wqkv = d_in[1], *wo = d_in[2], *wg = d_in[4], *wu = d_in[5], *wd = d_in[6];
  Params p;
  const CUtensorMapSwizzle S128 = CU_TENSOR_MAP_SWIZZLE_128B, S64 = CU_TENSOR_MAP_SWIZZLE_64B;
  make_map(enc, &p.x, x, 2, 448, 2048, 1, 896, 0, 64, 64, 1, S128);
  make_map(enc, &p.wqkv, wqkv, 3, 448, 448, 3, 2688, 896, 56, 16, 3, S128);
  for (int i = 0; i < 2; i++) {
    const void* w = i ? wu : wg;
    make_map(enc, &p.w1[i], w, 2, 1792, 448, 1, 3584, 0, 64, 64, 1, S128);
    make_map(enc, &p.wh[i], w, 2, 1792, 448, 1, 3584, 0, 32, 32, 1, S64);
  }
  make_map(enc, &p.wd, wd, 2, 448, 1792, 1, 896, 0, 64, 112, 1, S128);
  make_map(enc, &p.wo, wo, 2, 448, 448, 1, 896, 0, 64, 32, 1, S128);
  p.kv = (char*)kv;
  make_map(enc, &p.out, d_out, 2, 448, 2048, 1, 896, 0, 64, 16, 1, S128);
  p.gate_w = (const __nv_bfloat16*)d_in[7];
  p.outp = (uint4*)d_out;
  p.sync = (uint32_t*)sync;
  p.pf[0] = (const char*)wqkv; p.pf[1] = (const char*)wg; p.pf[2] = (const char*)wu; p.pf[3] = (const char*)wd; p.pf[4] = (const char*)wo;
  fused_kernel<<<128, 384, SMEM_BYTES>>>(p);
}
```
